```python
import torch

def _softmax(x, axis=-1):
    return torch.softmax(x, dim=axis)
def _gelu(x):
    return torch.nn.functional.gelu(x, approximate="tanh")
def _silu(x):
    return torch.nn.functional.silu(x)
def _sigmoid(x):
    return torch.sigmoid(x)
def _layernorm(x, axis=-1, eps=1e-5):
    m = x.mean(dim=axis, keepdim=True)
    v = x.var(dim=axis, keepdim=True, unbiased=False)
    return (x - m) / torch.sqrt(v + eps)
def _scatter_add(tgt, idx, src, axis=0):
    return tgt.clone().index_add_(axis, idx, src)
def _segment_sum(src, seg, n):
    out = torch.zeros((n,) + src.shape[1:], dtype=src.dtype)
    return out.index_add_(0, seg, src)
def _pad(x, pw):
    flat = tuple(v for pair in reversed(pw) for v in pair)
    return torch.nn.functional.pad(x, flat)

kernel_name = 'parallel_sum__ssm_conv_s4d__geglu_ffn__prompt'

def setup_inputs():

    _w = (lambda a: (lambda t: t.to(torch.bfloat16) if t.is_floating_point() else t)(torch.as_tensor(a)))
    def _A_setup():
        Bsz, L, D, N = 1, 2048, 512, 128
        return {
            "u": _w((lambda *s: torch.randn(*s, dtype=torch.bfloat16) * 0.05)(Bsz, L, D)),
            "log_A_real": _w((lambda *s: torch.randn(*s, dtype=torch.bfloat16) * 3.2)(D, N) * 0.5),
            "A_imag": _w((lambda *s: torch.randn(*s, dtype=torch.bfloat16) * 0.1)(D, N) * 3.14),
            "C_real": _w((lambda *s: torch.randn(*s, dtype=torch.bfloat16) * 1.6)(D, N) / N ** 0.5),
            "C_imag": _w((lambda *s: torch.randn(*s, dtype=torch.bfloat16) * 1.6)(D, N) / N ** 0.5),
            "log_dt": _w((lambda *s: torch.randn(*s, dtype=torch.bfloat16) * 0.1)(D) * 0.5 - 4.0),
            "D_skip": _w((lambda *s: torch.randn(*s, dtype=torch.bfloat16) * 0.2)(D)),
        }
    _A_in = _A_setup()

    def _B_setup():
        B, S, D, F = 1, 2048, 512, 1376
        return {
            "x": _w((lambda *s: torch.randn(*s, dtype=torch.bfloat16) * 0.05)(B, S, D)),
            "w_gate": _w((lambda *s: torch.randn(*s, dtype=torch.bfloat16) * 0.05)(D, F)),
            "w_up": _w((lambda *s: torch.randn(*s, dtype=torch.bfloat16) * 0.05)(D, F)),
            "w_down": _w((lambda *s: torch.randn(*s, dtype=torch.bfloat16) * 0.05)(F, D)),
        }
    _B_in = _B_setup()

    return {
        "A_u": _A_in["u"],
        "A_log_A_real": _A_in["log_A_real"],
        "A_A_imag": _A_in["A_imag"],
        "A_C_real": _A_in["C_real"],
        "A_C_imag": _A_in["C_imag"],
        "A_log_dt": _A_in["log_dt"],
        "A_D_skip": _A_in["D_skip"],
        "B_x": _B_in["x"],
        "B_w_gate": _B_in["w_gate"],
        "B_w_up": _B_in["w_up"],
        "B_w_down": _B_in["w_down"],
    }

def reference(A_u, A_log_A_real, A_A_imag, A_C_real, A_C_imag, A_log_dt, A_D_skip, B_x, B_w_gate, B_w_up, B_w_down):
    def _A_ref(u, log_A_real, A_imag, C_real, C_imag, log_dt, D_skip):
        L = u.shape[1]
        dt = torch.exp(log_dt)
        A = -torch.exp(log_A_real) + 1j * A_imag
        C = (C_real + 1j * C_imag) * dt[:, None]
        pos = (lambda x, dt: x.to(dt))(torch.arange(L), log_dt.dtype)
        P = torch.exp((A * dt[:, None])[:, :, None] * pos[None, None, :])
        K = 2.0 * torch.einsum("dn,dnl->dl", C, P).real
        L2 = 2 * L
        u_t = (lambda x, *d: x.permute(*d))(u, 0, 2, 1)
        Kf = (lambda x, *a, **k: torch.fft.rfft(x.float(), *a, **k))(K, L2)
        Uf = (lambda x, *a, **k: torch.fft.rfft(x.float(), *a, **k))(u_t, L2)
        y = (lambda x, *a, **k: torch.fft.irfft(x, *a, **k).to(torch.bfloat16))(Uf * Kf[None, :, :], L2)[:, :, :L]
        y = (lambda x, *d: x.permute(*d))(y, 0, 2, 1)
        return y + u * D_skip[None, None, :]

    def _B_ref(x, w_gate, w_up, w_down):
        return (_gelu(x @ w_gate) * (x @ w_up)) @ w_down

    x = A_u
    xn = _layernorm(x, axis=-1)
    return x + _A_ref(xn, A_log_A_real, A_A_imag, A_C_real, A_C_imag, A_log_dt, A_D_skip) + _B_ref(xn, B_w_gate, B_w_up, B_w_down)
```

```cpp
#include <cuda_runtime.h>
#include <cuda_bf16.h>
#include <cuda_fp16.h>
#include <cuda.h>
#include <stdint.h>

#define DEVINL __device__ __forceinline__

namespace fk {

constexpr int L_ = 2048, D_ = 512, NM_ = 128, F_ = 1376;
constexpr int BF = 176;
constexpr int NST1 = 7, ST_BYTES = 32768;
constexpr int OFF_KG = 163840;
constexpr int OFF_BAR = NST1 * ST_BYTES;
constexpr int SMEM_BYTES = OFF_BAR + 512;
constexpr int NTHREADS = 384;
constexpr int G1_ITERS = 16;
constexpr int G2_ITERS = 11;

constexpr int STG_BYTES = 64 * BF * 2;
constexpr int U_PL = 136 * 16, W5_PL = 113 * 16, W3_PL = 97 * 16, W9_PL = 80 * 16, W7_PL = 65 * 16;
constexpr int WO_W5 = 0;
constexpr int WO_W3 = WO_W5 + 2 * W5_PL;
constexpr int WO_W9 = WO_W3 + 2 * W3_PL;
constexpr int WO_W7 = WO_W9 + 2 * W9_PL;
constexpr int WORK_BYTES = WO_W7 + 2 * W7_PL;
constexpr int OFF_WORK = 46080;
constexpr int TD_P = 272, T2_P = 48, T3_P = 80;
constexpr int TO_TD = 0;
constexpr int TO_T2 = TO_TD + 2 * TD_P * 4;
constexpr int TO_T3 = TO_T2 + 8 * T2_P * 4;
constexpr int TO_MISC = TO_T3 + 4 * T3_P * 4;
constexpr int TAB_BYTES = 5120;
constexpr int IN_BYTES = 2 * U_PL + TAB_BYTES;
constexpr int OFF_IN = 131072 - 4 * IN_BYTES;
constexpr int OFF_XCH = OFF_WORK;
constexpr int OFF_EX = 94208, OFF_EA = 110592;
static_assert(TO_MISC + 16 <= TAB_BYTES, "table overflow");
static_assert(2 * STG_BYTES <= OFF_WORK && OFF_WORK + 4 * WORK_BYTES <= OFF_IN, "layout");

__device__ __align__(1024) __nv_bfloat16 g_xn[L_ * D_];
__device__ __align__(1024) __half g_xnT[D_ * L_];
__device__ __align__(1024) uint8_t g_tab[D_ * TAB_BYTES];
__device__ __align__(1024) __nv_bfloat16 g_h[L_ * F_];
__device__ __align__(1024) __nv_bfloat16 g_AT[D_ * L_];
__device__ unsigned int g_cnt[32 * 48];

#define TMARK(k) do {} while (0)

struct Params {
    const __nv_bfloat16 *x, *lar, *aim, *cre, *cim, *ldt, *dsk;
};

DEVINL uint32_t s2u(const void* p) { return (uint32_t)__cvta_generic_to_shared(p); }
DEVINL void mbar_init(uint32_t b, int c) { asm volatile("mbarrier.init.shared.b64 [%0], %1;" ::"r"(b), "r"(c)); }
DEVINL void mbar_expect(uint32_t b, int bytes) {
    asm volatile("mbarrier.arrive.expect_tx.shared.b64 _, [%0], %1;" ::"r"(b), "r"(bytes) : "memory");
}
DEVINL void mbar_arrive(uint32_t b) { asm volatile("mbarrier.arrive.shared.b64 _, [%0];" ::"r"(b) : "memory"); }
DEVINL void mbar_arrive_cta(uint32_t b, uint32_t cta) {
    uint32_t ra;
    asm volatile("mapa.shared::cluster.u32 %0, %1, %2;" : "=r"(ra) : "r"(b), "r"(cta));
    asm volatile("mbarrier.arrive.shared::cluster.b64 _, [%0];" ::"r"(ra) : "memory");
}
DEVINL void mbar_arrive_cta_n(uint32_t b, uint32_t cta, uint32_t n) {
    uint32_t ra;
    asm volatile("mapa.shared::cluster.u32 %0, %1, %2;" : "=r"(ra) : "r"(b), "r"(cta));
    asm volatile("mbarrier.arrive.shared::cluster.b64 _, [%0], %1;" ::"r"(ra), "r"(n) : "memory");
}
DEVINL bool mbar_try(uint32_t b, int ph) {
    uint32_t ok;
    asm volatile("{\n.reg .pred p;\nmbarrier.try_wait.parity.shared.b64 p, [%1], %2;\nselp.u32 %0,1,0,p;\n}"
                 : "=r"(ok) : "r"(b), "r"(ph) : "memory");
    return ok;
}
DEVINL void mbar_wait(uint32_t b, int ph) {
    int n = 0;
    while (!mbar_try(b, ph)) { if (++n > (1 << 22)) break; }
}
DEVINL void tma2d(uint32_t dst, const CUtensorMap* tm, int c0, int c1, uint32_t bar) {
    asm volatile("cp.async.bulk.tensor.2d.shared::cluster.global.mbarrier::complete_tx::bytes [%0], [%1, {%3, %4}], [%2];"
                 ::"r"(dst), "l"(tm), "r"(bar), "r"(c0), "r"(c1) : "memory");
}
DEVINL void tma2d_mc(uint32_t dst, const CUtensorMap* tm, int c0, int c1, uint32_t bar, uint16_t mask) {
    asm volatile("cp.async.bulk.tensor.2d.shared::cluster.global.mbarrier::complete_tx::bytes.multicast::cluster [%0], [%1, {%3, %4}], [%2], %5;"
                 ::"r"(dst), "l"(tm), "r"(bar), "r"(c0), "r"(c1), "h"(mask) : "memory");
}
DEVINL void tma3d(uint32_t dst, const CUtensorMap* tm, int c0, int c1, int c2, uint32_t bar) {
    asm volatile("cp.async.bulk.tensor.3d.shared::cluster.global.mbarrier::complete_tx::bytes [%0], [%1, {%3, %4, %5}], [%2];"
                 ::"r"(dst), "l"(tm), "r"(bar), "r"(c0), "r"(c1), "r"(c2) : "memory");
}
DEVINL void tma4d(uint32_t dst, const CUtensorMap* tm, int c0, int c1, int c2, int c3, uint32_t bar) {
    asm volatile("cp.async.bulk.tensor.4d.shared::cluster.global.mbarrier::complete_tx::bytes [%0], [%1, {%3, %4, %5, %6}], [%2];"
                 ::"r"(dst), "l"(tm), "r"(bar), "r"(c0), "r"(c1), "r"(c2), "r"(c3) : "memory");
}
DEVINL void bulk_load(uint32_t dst, const void* src, int bytes, uint32_t bar) {
    asm volatile("cp.async.bulk.shared::cluster.global.mbarrier::complete_tx::bytes [%0], [%1], %2, [%3];"
                 ::"r"(dst), "l"(src), "r"(bytes), "r"(bar) : "memory");
}
DEVINL void bulk_store(void* dst, uint32_t src, int bytes) {
    asm volatile("cp.async.bulk.global.shared::cta.bulk_group [%0], [%1], %2;" ::"l"(dst), "r"(src), "r"(bytes) : "memory");
}
DEVINL void tma3d_store(const CUtensorMap* tm, int c0, int c1, int c2, uint32_t src) {
    asm volatile("cp.async.bulk.tensor.3d.global.shared::cta.bulk_group [%0, {%2, %3, %4}], [%1];"
                 ::"l"(tm), "r"(src), "r"(c0), "r"(c1), "r"(c2) : "memory");
}
DEVINL void tma2d_store(const CUtensorMap* tm, int c0, int c1, uint32_t src) {
    asm volatile("cp.async.bulk.tensor.2d.global.shared::cta.bulk_group [%0, {%2, %3}], [%1];"
                 ::"l"(tm), "r"(src), "r"(c0), "r"(c1) : "memory");
}
DEVINL void bulk_commit() { asm volatile("cp.async.bulk.commit_group;" ::: "memory"); }
DEVINL void bulk_wait0() { asm volatile("cp.async.bulk.wait_group 0;" ::: "memory"); }
DEVINL void bulk_wait_read0() { asm volatile("cp.async.bulk.wait_group.read 0;" ::: "memory"); }
DEVINL void fence_async() { asm volatile("fence.proxy.async;" ::: "memory"); }
DEVINL void fence_async_smem() { asm volatile("fence.proxy.async.shared::cta;" ::: "memory"); }
DEVINL void bar_sync(int id, int n) { asm volatile("bar.sync %0, %1;" ::"r"(id), "r"(n) : "memory"); }
DEVINL void bar_arrive(int id, int n) { asm volatile("bar.arrive %0, %1;" ::"r"(id), "r"(n) : "memory"); }
DEVINL void cluster_sync() {
    asm volatile("barrier.cluster.arrive.relaxed.aligned;\nbarrier.cluster.wait.aligned;" ::: "memory");
}
DEVINL void cluster_arrive() { asm volatile("barrier.cluster.arrive.relaxed.aligned;" ::: "memory"); }
DEVINL void cluster_wait() { asm volatile("barrier.cluster.wait.acquire.aligned;" ::: "memory"); }
DEVINL unsigned ld_acquire(const unsigned* p) {
    unsigned v;
    asm volatile("ld.acquire.gpu.global.u32 %0, [%1];" : "=r"(v) : "l"(p) : "memory");
    return v;
}
DEVINL void red_release(unsigned* p, unsigned v) {
    asm volatile("red.release.gpu.global.add.u32 [%0], %1;" ::"l"(p), "r"(v) : "memory");
}
DEVINL void red_relaxed(unsigned* p, unsigned v) {
    asm volatile("red.relaxed.gpu.global.add.u32 [%0], %1;" ::"l"(p), "r"(v) : "memory");
}
DEVINL unsigned ld_relaxed(const unsigned* p) {
    unsigned v;
    asm volatile("ld.relaxed.gpu.global.u32 %0, [%1];" : "=r"(v) : "l"(p) : "memory");
    return v;
}
DEVINL void wait_counter(const unsigned* p, unsigned target) {
    int n = 0;
    while ((int)(ld_relaxed(p) - target) < 0) { if (++n > (1 << 22)) break; }
}
DEVINL void st_async4(uint32_t raddr, float a, float b, float c, float d, uint32_t rbar) {
    asm volatile("st.async.weak.shared::cluster.mbarrier::complete_tx::bytes.v4.f32 [%0], {%1,%2,%3,%4}, [%5];"
                 ::"r"(raddr), "f"(a), "f"(b), "f"(c), "f"(d), "r"(rbar) : "memory");
}
DEVINL uint32_t mapa(uint32_t a, uint32_t cta) {
    uint32_t ra;
    asm volatile("mapa.shared::cluster.u32 %0, %1, %2;" : "=r"(ra) : "r"(a), "r"(cta));
    return ra;
}
DEVINL void sts64(uint32_t a, uint32_t x, uint32_t y) { asm volatile("st.shared.v2.u32 [%0], {%1,%2};" ::"r"(a), "r"(x), "r"(y) : "memory"); }
DEVINL void ldsm4(uint32_t a, uint32_t& r0, uint32_t& r1, uint32_t& r2, uint32_t& r3) {
    asm volatile("ldmatrix.sync.aligned.m8n8.x4.shared.b16 {%0,%1,%2,%3}, [%4];"
                 : "=r"(r0), "=r"(r1), "=r"(r2), "=r"(r3) : "r"(a) : "memory");
}
DEVINL void ldsm4t(uint32_t a, uint32_t& r0, uint32_t& r1, uint32_t& r2, uint32_t& r3) {
    asm volatile("ldmatrix.sync.aligned.m8n8.x4.trans.shared.b16 {%0,%1,%2,%3}, [%4];"
                 : "=r"(r0), "=r"(r1), "=r"(r2), "=r"(r3) : "r"(a) : "memory");
}
DEVINL void stsm4(uint32_t a, uint32_t r0, uint32_t r1, uint32_t r2, uint32_t r3) {
    asm volatile("stmatrix.sync.aligned.m8n8.x4.shared.b16 [%0], {%1,%2,%3,%4};"
                 ::"r"(a), "r"(r0), "r"(r1), "r"(r2), "r"(r3) : "memory");
}
DEVINL void stsm4t(uint32_t a, uint32_t r0, uint32_t r1, uint32_t r2, uint32_t r3) {
    asm volatile("stmatrix.sync.aligned.m8n8.x4.trans.shared.b16 [%0], {%1,%2,%3,%4};"
                 ::"r"(a), "r"(r0), "r"(r1), "r"(r2), "r"(r3) : "memory");
}
DEVINL void mma_f16(float (&c)[4], uint32_t a0, uint32_t a1, uint32_t a2, uint32_t a3, uint32_t b0, uint32_t b1) {
    asm volatile("mma.sync.aligned.m16n8k16.row.col.f32.f16.f16.f32 {%0,%1,%2,%3},{%4,%5,%6,%7},{%8,%9},{%0,%1,%2,%3};"
                 : "+f"(c[0]), "+f"(c[1]), "+f"(c[2]), "+f"(c[3])
                 : "r"(a0), "r"(a1), "r"(a2), "r"(a3), "r"(b0), "r"(b1));
}
DEVINL uint32_t lds32(uint32_t a) { uint32_t v; asm volatile("ld.shared.u32 %0, [%1];" : "=r"(v) : "r"(a) : "memory"); return v; }
DEVINL uint16_t lds16(uint32_t a) { uint16_t v; asm volatile("ld.shared.u16 %0, [%1];" : "=h"(v) : "r"(a) : "memory"); return v; }
DEVINL float ldsf(uint32_t a) { float v; asm volatile("ld.shared.f32 %0, [%1];" : "=f"(v) : "r"(a) : "memory"); return v; }
DEVINL uint4 lds128(uint32_t a) {
    uint4 v;
    asm volatile("ld.shared.v4.u32 {%0,%1,%2,%3}, [%4];" : "=r"(v.x), "=r"(v.y), "=r"(v.z), "=r"(v.w) : "r"(a) : "memory");
    return v;
}
DEVINL void sts32(uint32_t a, uint32_t v) { asm volatile("st.shared.u32 [%0], %1;" ::"r"(a), "r"(v) : "memory"); }
DEVINL void sts16(uint32_t a, uint16_t v) { asm volatile("st.shared.u16 [%0], %1;" ::"r"(a), "h"(v) : "memory"); }
DEVINL void stsf(uint32_t a, float v) { asm volatile("st.shared.f32 [%0], %1;" ::"r"(a), "f"(v) : "memory"); }
DEVINL void sts128(uint32_t a, uint4 v) {
    asm volatile("st.shared.v4.u32 [%0], {%1,%2,%3,%4};" ::"r"(a), "r"(v.x), "r"(v.y), "r"(v.z), "r"(v.w) : "memory");
}
template <int SW = 1>
DEVINL uint64_t mkdesc(uint32_t addr, uint32_t lbo, uint32_t sbo) {
    return (uint64_t)((addr & 0x3FFFF) >> 4) | ((uint64_t)((lbo & 0x3FFFF) >> 4) << 16) |
           ((uint64_t)((sbo & 0x3FFFF) >> 4) << 32) | ((uint64_t)SW << 62);
}
#define WG_FENCE asm volatile("wgmma.fence.sync.aligned;" ::: "memory")
#define WG_COMMIT asm volatile("wgmma.commit_group.sync.aligned;" ::: "memory")
#define WG_WAIT(n) asm volatile("wgmma.wait_group.sync.aligned %0;" ::"n"(n) : "memory")

template<int TA, int TB>
__device__ __forceinline__ void wgmma_ss_bf16_n176(float (&d)[88], uint64_t da, uint64_t db, int scaleD) {
  asm volatile("{\n.reg .pred p;\nsetp.ne.b32 p, %90, 0;\n"
    "wgmma.mma_async.sync.aligned.m64n176k16.f32.bf16.bf16 {%0, %1, %2, %3, %4, %5, %6, %7, %8, %9, %10, %11, %12, %13, %14, %15, %16, %17, %18, %19, %20, %21, %22, %23, %24, %25, %26, %27, %28, %29, %30, %31, %32, %33, %34, %35, %36, %37, %38, %39, %40, %41, %42, %43, %44, %45, %46, %47, %48, %49, %50, %51, %52, %53, %54, %55, %56, %57, %58, %59, %60, %61, %62, %63, %64, %65, %66, %67, %68, %69, %70, %71, %72, %73, %74, %75, %76, %77, %78, %79, %80, %81, %82, %83, %84, %85, %86, %87}, %88, %89, p, 1, 1, %91, %92;\n}\n"
    : "+f"(d[0]), "+f"(d[1]), "+f"(d[2]), "+f"(d[3]), "+f"(d[4]), "+f"(d[5]), "+f"(d[6]), "+f"(d[7]), "+f"(d[8]), "+f"(d[9]), "+f"(d[10]), "+f"(d[11]), "+f"(d[12]), "+f"(d[13]), "+f"(d[14]), "+f"(d[15]), "+f"(d[16]), "+f"(d[17]), "+f"(d[18]), "+f"(d[19]), "+f"(d[20]), "+f"(d[21]), "+f"(d[22]), "+f"(d[23]), "+f"(d[24]), "+f"(d[25]), "+f"(d[26]), "+f"(d[27]), "+f"(d[28]), "+f"(d[29]), "+f"(d[30]), "+f"(d[31]), "+f"(d[32]), "+f"(d[33]), "+f"(d[34]), "+f"(d[35]), "+f"(d[36]), "+f"(d[37]), "+f"(d[38]), "+f"(d[39]), "+f"(d[40]), "+f"(d[41]), "+f"(d[42]), "+f"(d[43]), "+f"(d[44]), "+f"(d[45]), "+f"(d[46]), "+f"(d[47]), "+f"(d[48]), "+f"(d[49]), "+f"(d[50]), "+f"(d[51]), "+f"(d[52]), "+f"(d[53]), "+f"(d[54]), "+f"(d[55]), "+f"(d[56]), "+f"(d[57]), "+f"(d[58]), "+f"(d[59]), "+f"(d[60]), "+f"(d[61]), "+f"(d[62]), "+f"(d[63]), "+f"(d[64]), "+f"(d[65]), "+f"(d[66]), "+f"(d[67]), "+f"(d[68]), "+f"(d[69]), "+f"(d[70]), "+f"(d[71]), "+f"(d[72]), "+f"(d[73]), "+f"(d[74]), "+f"(d[75]), "+f"(d[76]), "+f"(d[77]), "+f"(d[78]), "+f"(d[79]), "+f"(d[80]), "+f"(d[81]), "+f"(d[82]), "+f"(d[83]), "+f"(d[84]), "+f"(d[85]), "+f"(d[86]), "+f"(d[87])
    : "l"(da), "l"(db), "r"(scaleD), "n"(TA), "n"(TB));
}
template<int TA, int TB>
__device__ __forceinline__ void wgmma_ss_bf16_n128(float (&d)[64], uint64_t da, uint64_t db, int scaleD) {
  asm volatile("{\n.reg .pred p;\nsetp.ne.b32 p, %66, 0;\n"
    "wgmma.mma_async.sync.aligned.m64n128k16.f32.bf16.bf16 {%0, %1, %2, %3, %4, %5, %6, %7, %8, %9, %10, %11, %12, %13, %14, %15, %16, %17, %18, %19, %20, %21, %22, %23, %24, %25, %26, %27, %28, %29, %30, %31, %32, %33, %34, %35, %36, %37, %38, %39, %40, %41, %42, %43, %44, %45, %46, %47, %48, %49, %50, %51, %52, %53, %54, %55, %56, %57, %58, %59, %60, %61, %62, %63}, %64, %65, p, 1, 1, %67, %68;\n}\n"
    : "+f"(d[0]), "+f"(d[1]), "+f"(d[2]), "+f"(d[3]), "+f"(d[4]), "+f"(d[5]), "+f"(d[6]), "+f"(d[7]), "+f"(d[8]), "+f"(d[9]), "+f"(d[10]), "+f"(d[11]), "+f"(d[12]), "+f"(d[13]), "+f"(d[14]), "+f"(d[15]), "+f"(d[16]), "+f"(d[17]), "+f"(d[18]), "+f"(d[19]), "+f"(d[20]), "+f"(d[21]), "+f"(d[22]), "+f"(d[23]), "+f"(d[24]), "+f"(d[25]), "+f"(d[26]), "+f"(d[27]), "+f"(d[28]), "+f"(d[29]), "+f"(d[30]), "+f"(d[31]), "+f"(d[32]), "+f"(d[33]), "+f"(d[34]), "+f"(d[35]), "+f"(d[36]), "+f"(d[37]), "+f"(d[38]), "+f"(d[39]), "+f"(d[40]), "+f"(d[41]), "+f"(d[42]), "+f"(d[43]), "+f"(d[44]), "+f"(d[45]), "+f"(d[46]), "+f"(d[47]), "+f"(d[48]), "+f"(d[49]), "+f"(d[50]), "+f"(d[51]), "+f"(d[52]), "+f"(d[53]), "+f"(d[54]), "+f"(d[55]), "+f"(d[56]), "+f"(d[57]), "+f"(d[58]), "+f"(d[59]), "+f"(d[60]), "+f"(d[61]), "+f"(d[62]), "+f"(d[63])
    : "l"(da), "l"(db), "r"(scaleD), "n"(TA), "n"(TB));
}

DEVINL float bf_lo(uint32_t v) { return __uint_as_float(v << 16); }
DEVINL float bf_hi(uint32_t v) { return __uint_as_float(v & 0xFFFF0000u); }
DEVINL float bfr(float x) {
    uint32_t r;
    asm("cvt.rn.bf16x2.f32 %0, %1, %2;" : "=r"(r) : "f"(x), "f"(0.f));
    return __uint_as_float(r);
}
DEVINL uint32_t pack_bf(float lo, float hi) {
    uint32_t r;
    asm("cvt.rn.bf16x2.f32 %0, %1, %2;" : "=r"(r) : "f"(hi), "f"(lo));
    return r;
}
DEVINL uint32_t pack_h(float lo, float hi) {
    uint32_t r;
    asm("cvt.rn.f16x2.f32 %0, %1, %2;" : "=r"(r) : "f"(hi), "f"(lo));
    return r;
}
DEVINL float h_lo(uint32_t v) { return __half2float(__ushort_as_half((unsigned short)(v & 0xFFFF))); }
DEVINL float h_hi(uint32_t v) { return __half2float(__ushort_as_half((unsigned short)(v >> 16))); }
DEVINL float ex2f(float x) { float r; asm("ex2.approx.ftz.f32 %0, %1;" : "=f"(r) : "f"(x)); return r; }
DEVINL float rcp_ap(float x) { float r; asm("rcp.approx.ftz.f32 %0, %1;" : "=f"(r) : "f"(x)); return r; }
DEVINL float sqrt_ap(float x) { float r; asm("sqrt.approx.f32 %0, %1;" : "=f"(r) : "f"(x)); return r; }
DEVINL float exp_ap(float x) { return ex2f(x * 1.4426950408889634f); }
DEVINL float tanh_ap(float x) { float r; asm("tanh.approx.f32 %0, %1;" : "=f"(r) : "f"(x)); return r; }
DEVINL float2 cmul(float2 a, float2 b) {
    return make_float2(fmaf(a.x, b.x, -a.y * b.y), fmaf(a.x, b.y, a.y * b.x));
}
DEVINL float2 cexpb(float a2, float w, float b) {
    float mag = ex2f(a2 * b);
    float t = w * b;
    t = t - rintf(t);
    float ang = t * 6.283185307179586f;
    return make_float2(mag * __cosf(ang), mag * __sinf(ang));
}
DEVINL float2 shfl2(float2 v, int src) {
    return make_float2(__shfl_sync(0xffffffffu, v.x, src), __shfl_sync(0xffffffffu, v.y, src));
}
DEVINL float pow2_scale(float mx, int target_exp) {
    int e = (int)((__float_as_uint(mx) >> 23) & 0xFF);
    if (e == 0 || e == 255) return 1.0f;
    int se = 127 + target_exp - (e - 127);
    se = max(1, min(254, se));
    return __uint_as_float((uint32_t)se << 23);
}

constexpr int KG_PITCH = 144;
struct KgIn { uint2 ca, cb; uint32_t vl, vi, vr, vc; uint16_t ldt; };
DEVINL KgIn kgen_load(const Params& P, int ch, int w2, int lane) {
    KgIn k;
    k.ca = __ldg(reinterpret_cast<const uint2*>(P.cre + ch * NM_ + lane * 4));
    k.cb = __ldg(reinterpret_cast<const uint2*>(P.cim + ch * NM_ + lane * 4));
    const int n = ch * NM_ + 64 * w2 + 2 * lane;
    k.vl = __ldg(reinterpret_cast<const uint32_t*>(P.lar + n));
    k.vi = __ldg(reinterpret_cast<const uint32_t*>(P.aim + n));
    k.vr = __ldg(reinterpret_cast<const uint32_t*>(P.cre + n));
    k.vc = __ldg(reinterpret_cast<const uint32_t*>(P.cim + n));
    k.ldt = __ldg(reinterpret_cast<const uint16_t*>(P.ldt + ch));
    return k;
}

DEVINL void kgen(const KgIn& in, uint32_t kg, uint32_t kgp, int w2, int lane, int barid) {
    const int g = lane >> 2, c = lane & 3, lm = lane >> 3, lr = lane & 7;
    const float dt = bfr(exp_ap(__uint_as_float((uint32_t)in.ldt << 16)));
    float mx;
    {
        const uint2 a = in.ca, b = in.cb;
        mx = fmaxf(fmaxf(fabsf(bf_lo(a.x)), fabsf(bf_hi(a.x))), fmaxf(fabsf(bf_lo(a.y)), fabsf(bf_hi(a.y))));
        mx = fmaxf(mx, fmaxf(fmaxf(fabsf(bf_lo(b.x)), fabsf(bf_hi(b.x))), fmaxf(fabsf(bf_lo(b.y)), fabsf(bf_hi(b.y)))));
#pragma unroll
        for (int o = 16; o; o >>= 1) mx = fmaxf(mx, __shfl_xor_sync(0xffffffffu, mx, o));
    }
    const float gs = pow2_scale(2.f * dt * mx, 13);
    float acc[3][2][4];
#pragma unroll
    for (int i = 0; i < 3; i++)
#pragma unroll
        for (int j = 0; j < 2; j++) acc[i][j][0] = acc[i][j][1] = acc[i][j][2] = acc[i][j][3] = 0.f;
    const uint32_t wa = kg + lane * 4;
    const uint32_t la = kg + ((lm & 1) * 8 + lr) * KG_PITCH + (lm >> 1) * 16;
    const uint32_t lb = kg + (41 + (lm >> 1) * 8 + lr) * KG_PITCH + (lm & 1) * 16;
#pragma unroll 1
    for (int bt = 0; bt < 2; bt++) {
        const float a2 = -bfr(exp_ap(bt ? bf_hi(in.vl) : bf_lo(in.vl))) * dt * 1.4426950408889634f;
        const float w = (bt ? bf_hi(in.vi) : bf_lo(in.vi)) * dt * 0.15915494309189535f;
        const float2 Cc = make_float2((bt ? bf_hi(in.vr) : bf_lo(in.vr)) * dt * 2.f * gs, (bt ? bf_hi(in.vc) : bf_lo(in.vc)) * dt * 2.f * gs);
        const float2 z1 = cexpb(a2, w, 1.f), z8 = cexpb(a2, w, 8.f), z128 = cexpb(a2, w, 128.f);
        {
            float2 E[9];
            E[1] = z8;
            E[2] = cmul(z8, z8);
            E[4] = cmul(E[2], E[2]);
            E[8] = cmul(E[4], E[4]);
            E[3] = cmul(E[2], E[1]);
#pragma unroll
            for (int p = 5; p < 8; p++) E[p] = cmul(E[4], E[p - 4]);
            sts32(wa + 41 * KG_PITCH, pack_h(1.f, 0.f));
#pragma unroll
            for (int p = 1; p < 9; p++) sts32(wa + (41 + p) * KG_PITCH, pack_h(E[p].x, -E[p].y));
#pragma unroll
            for (int p = 9; p < 16; p++) { const float2 v = cmul(E[8], E[p - 8]); sts32(wa + (41 + p) * KG_PITCH, pack_h(v.x, -v.y)); }
        }
        float2 X[8];
        X[1] = z1;
        X[2] = cmul(z1, z1);
        X[4] = cmul(X[2], X[2]);
        X[3] = cmul(X[2], X[1]);
#pragma unroll
        for (int e = 5; e < 8; e++) X[e] = cmul(X[4], X[e - 4]);
        const float2 Z2 = cmul(z128, z128), Z4 = cmul(Z2, Z2), Z8 = cmul(Z4, Z4);
        float2 H[9];
        H[0] = Cc;
        H[1] = cmul(Cc, z128);
        H[2] = cmul(H[0], Z2); H[3] = cmul(H[1], Z2);
#pragma unroll
        for (int p = 4; p < 8; p++) H[p] = cmul(H[p - 4], Z4);
#define PUTG(row, v) do { const float2 _v = (v); sts32(wa + (row) * KG_PITCH, pack_h(_v.x, _v.y)); } while (0)
#pragma unroll
        for (int p = 0; p < 2; p++) {
            PUTG(8 * p, H[p]);
#pragma unroll
            for (int e = 1; e < 8; e++) PUTG(8 * p + e, cmul(H[p], X[e]));
        }
#pragma unroll
        for (int p = 2; p < 4; p++) {
            PUTG(16 + 4 * (p - 2), H[p]);
#pragma unroll
            for (int e = 1; e < 4; e++) PUTG(16 + 4 * (p - 2) + e, cmul(H[p], X[2 * e]));
        }
#pragma unroll
        for (int p = 4; p < 8; p++) {
            PUTG(24 + 2 * (p - 4), H[p]);
            PUTG(25 + 2 * (p - 4), cmul(H[p], X[4]));
        }
        H[8] = cmul(H[0], Z8);
        PUTG(32, H[8]);
#pragma unroll
        for (int p = 1; p < 8; p++) PUTG(32 + p, cmul(H[p], Z8));
        PUTG(40, cmul(H[8], Z8));
#undef PUTG
        __syncwarp();
#pragma unroll
        for (int ks = 0; ks < 4; ks++) {
            uint32_t b0, b1, b2, b3;
            ldsm4(lb + ks * 32, b0, b1, b2, b3);
#pragma unroll
            for (int mt = 0; mt < 3; mt++) {
                uint32_t a0, a1, a2_, a3;
                ldsm4(la + mt * 16 * KG_PITCH + ks * 32, a0, a1, a2_, a3);
                mma_f16(acc[mt][0], a0, a1, a2_, a3, b0, b1);
                mma_f16(acc[mt][1], a0, a1, a2_, a3, b2, b3);
            }
        }
        __syncwarp();
    }
    if (threadIdx.x == 32) TMARK(22);
#pragma unroll
    for (int mt = 0; mt < 3; mt++) {
        const float v0 = w2 ? acc[mt][0][0] : acc[mt][1][0], v1 = w2 ? acc[mt][0][1] : acc[mt][1][1];
        const float v2 = w2 ? acc[mt][0][2] : acc[mt][1][2], v3 = w2 ? acc[mt][0][3] : acc[mt][1][3];
        sts128(kg + 6144 + (mt * 32 + lane) * 16, make_uint4(__float_as_uint(v0), __float_as_uint(v1), __float_as_uint(v2), __float_as_uint(v3)));
    }
    const uint32_t tab = w2 ? kgp : kg;
    bar_sync(barid, 64);
    {
        const uint4 z = make_uint4(0, 0, 0, 0);
#pragma unroll
        for (int i = 0; i < 5; i++) sts128(tab + ((i * 2 + w2) * 32 + lane) * 16, z);
    }
    float K[3][4];
    const float ginv = rcp_ap(gs);
    float km = 0.f;
#pragma unroll
    for (int mt = 0; mt < 3; mt++) {
        const uint4 o = lds128(kgp + 6144 + (mt * 32 + lane) * 16);
        K[mt][0] = ((w2 ? acc[mt][1][0] : acc[mt][0][0]) + __uint_as_float(o.x)) * ginv;
        K[mt][1] = ((w2 ? acc[mt][1][1] : acc[mt][0][1]) + __uint_as_float(o.y)) * ginv;
        K[mt][2] = ((w2 ? acc[mt][1][2] : acc[mt][0][2]) + __uint_as_float(o.z)) * ginv;
        K[mt][3] = ((w2 ? acc[mt][1][3] : acc[mt][0][3]) + __uint_as_float(o.w)) * ginv;
        if (mt == 2) { if (w2 != 0 || lane != 0) K[2][2] = 0.f; K[2][3] = 0.f; }
        km = fmaxf(km, fmaxf(fmaxf(fabsf(K[mt][0]), fabsf(K[mt][1])), fmaxf(fabsf(K[mt][2]), fabsf(K[mt][3]))));
    }
#pragma unroll
    for (int o = 16; o; o >>= 1) km = fmaxf(km, __shfl_xor_sync(0xffffffffu, km, o));
    if (lane == 0) {
        stsf(kg + 7936, km);
        if (w2 == 0) { stsf(kg + 7940, K[1][2]); stsf(kg + 7944, K[2][0]); }
    }
    bar_sync(barid, 64);
    if (threadIdx.x == 32) TMARK(25);
    const float ks = pow2_scale(fmaxf(km, ldsf(kgp + 7936)), 13);
    if (w2 == 1 && lane == 31) {
        K[1][1] -= ldsf(kgp + 7940);
        K[1][3] -= ldsf(kgp + 7944);
    }
    if (w2 == 0 && lane == 0) { stsf(tab + TO_MISC, rcp_ap(ks)); stsf(tab + TO_MISC + 4, K[2][0] * ks); }
#define TPUT(base, P_, i, v)                                              \
    do {                                                                  \
        const int _i = (i);                                               \
        const uint16_t _h = __half_as_ushort(__float2half_rn(v));         \
        sts16((base) + ((_i & 1) * (P_) + (_i >> 1)) * 4, _h);            \
        sts16((base) + (((_i + 1) & 1) * (P_) + ((_i + 1) >> 1)) * 4 + 2, _h); \
    } while (0)
#pragma unroll
    for (int e = 0; e < 2; e++) {
        const int p8 = 8 * (8 * w2 + 2 * c + e);
        const uint32_t td = tab + TO_TD + 8 * 4;
        TPUT(td, TD_P, g + p8, K[0][e] * ks);
        TPUT(td, TD_P, 128 + g + p8, K[0][2 + e] * ks);
        {
            const int p = 256 + 128 * (g >> 2) + 2 * (g & 3) + p8;
            const float v = K[1][e] * ks;
            TPUT(td, TD_P, p, v);
            if ((g & 1) == 0) {
                if (p > 256) TPUT(td, TD_P, p - 1, v);
                TPUT(td, TD_P, p + 1, v);
            }
        }
        {
            const int p = 512 + 128 * (g >> 1) + 4 * (g & 1) + p8;
            TPUT(tab + TO_T2 + (((p >> 2) & 3) * 2 * T2_P - 8) * 4, T2_P, p >> 4, K[1][2 + e] * ks);
        }
        {
            const int p = 1024 + 128 * g + p8;
            TPUT(tab + TO_T3 + (((p >> 3) & 1) * 2 * T3_P - 20) * 4, T3_P, p >> 4, K[2][e] * ks);
        }
    }
    if (w2 == 0 && lane == 0) TPUT(tab + TO_T3 - 20 * 4, T3_P, 128, K[2][2] * ks);
#undef TPUT
    if (threadIdx.x == 32) TMARK(26);
    fence_async_smem();
}

template <int HALF>
DEVINL void conv_channel(float dsk, uint32_t ib, uint32_t wb, uint32_t os0, uint32_t os0bar, int lane, uint32_t winbar, uint32_t inbar, uint32_t donebar, __nv_bfloat16* gout) {
    constexpr int T0 = 8 * HALF;
    const int g = lane >> 2, c = lane & 3;
    const uint32_t U = ib, tab = ib + 2 * U_PL;
    if (HALF == 1) {
        const uint4 z = make_uint4(0, 0, 0, 0);
        sts128(wb + WO_W5 + (lane >> 4) * W5_PL + (lane & 15) * 16, z);
        if (lane < 31) sts128(wb + WO_W9 + (lane >> 4) * W9_PL + (lane & 15) * 16, z);
        if (lane == 0) sts128(wb + WO_W5 + 16 * 16, z);
        if (lane == 1) sts128(wb + WO_W3, z);
        if (lane == 2) sts128(wb + WO_W7, z);
    }
    mbar_wait(inbar, 0);
    if (threadIdx.x == 128) TMARK(17);
#pragma unroll 1
    for (int s = HALF ? lane - 1 : 127 + lane; s < (HALF ? 127 : 192); s += 32) {
        float u[24];
#pragma unroll
        for (int k = 0; k < 3; k++) {
            const int sg = s - 1 + k;
            const uint4 v = lds128(U + (sg & 1) * U_PL + ((sg >> 1) + 8) * 16);
            u[8 * k + 0] = h_lo(v.x); u[8 * k + 1] = h_hi(v.x); u[8 * k + 2] = h_lo(v.y); u[8 * k + 3] = h_hi(v.y);
            u[8 * k + 4] = h_lo(v.z); u[8 * k + 5] = h_hi(v.z); u[8 * k + 6] = h_lo(v.w); u[8 * k + 7] = h_hi(v.w);
        }
        float p2[22];
#pragma unroll
        for (int i = 3; i < 20; i++) p2[i] = u[i] + u[i + 1];
        float a3[8], a5[8];
#pragma unroll
        for (int i = 0; i < 8; i++) {
            a3[i] = p2[3 + i] + u[5 + i];
            a5[i] = (p2[6 + i] + p2[8 + i]) + u[10 + i];
        }
        sts128(wb + WO_W5 + (s & 1) * W5_PL + ((s >> 1) + 17) * 16,
               make_uint4(pack_h(a5[0], a5[1]), pack_h(a5[2], a5[3]), pack_h(a5[4], a5[5]), pack_h(a5[6], a5[7])));
        sts128(wb + WO_W3 + (s & 1) * W3_PL + ((s >> 1) + 1) * 16,
               make_uint4(pack_h(a3[0], a3[1]), pack_h(a3[2], a3[3]), pack_h(a3[4], a3[5]), pack_h(a3[6], a3[7])));
        if (s < 128) {
            float a7[8], a9[8];
#pragma unroll
            for (int i = 0; i < 8; i++) {
                a7[i] = a5[i] + (u[5 + i] + u[11 + i]);
                a9[i] = a5[i] + (p2[4 + i] + p2[11 + i]);
            }
            sts128(wb + WO_W9 + (s & 1) * W9_PL + ((s >> 1) + 16) * 16,
                   make_uint4(pack_h(a9[0], a9[1]), pack_h(a9[2], a9[3]), pack_h(a9[4], a9[5]), pack_h(a9[6], a9[7])));
            sts128(wb + WO_W7 + (s & 1) * W7_PL + ((s >> 1) + 1) * 16,
                   make_uint4(pack_h(a7[0], a7[1]), pack_h(a7[2], a7[3]), pack_h(a7[4], a7[5]), pack_h(a7[6], a7[7])));
        }
    }
    mbar_arrive(winbar);
    if (threadIdx.x == 128) TMARK(18);
    float acc[8][4];
#pragma unroll
    for (int t = 0; t < 8; t++) acc[t][0] = acc[t][1] = acc[t][2] = acc[t][3] = 0.f;
    const int par = g & 1, gh = g >> 1;
    const int lm = lane >> 3, lr = lane & 7;
    const uint32_t ub = U + (lm & 1) * U_PL + (8 + 8 * (lm >> 1) + lr) * 16;
    {
        constexpr int JP0 = HALF ? 2 : 0, NJP = HALF ? 6 : 4;
        const uint32_t td = tab + TO_TD + (par * TD_P + 8 + gh - c) * 4;
        uint32_t Fa[2][4][4], B[2][NJP][4];
#define DENSE_LOAD(buf, s_)                                                                                              \
        do {                                                                                                             \
            _Pragma("unroll") for (int d1 = 0; d1 < 4; d1++) {                                                           \
                const uint32_t a = td + 16 * (2 * (8 * d1 + (s_)));                                                      \
                Fa[buf][d1][0] = lds32(a); Fa[buf][d1][1] = lds32(a + 16); Fa[buf][d1][2] = lds32(a - 16); Fa[buf][d1][3] = lds32(a); \
            }                                                                                                            \
            _Pragma("unroll") for (int jp = 0; jp < NJP; jp++)                                                           \
                ldsm4(ub + (16 * (JP0 + jp) - (s_)) * 16, B[buf][jp][0], B[buf][jp][1], B[buf][jp][2], B[buf][jp][3]);   \
        } while (0)
#define DENSE_MMA(buf)                                                                                                   \
        do {                                                                                                             \
            _Pragma("unroll") for (int d1 = 0; d1 < 4; d1++) {                                                           \
                _Pragma("unroll") for (int j = 0; j < 2 * NJP; j++) {                                                    \
                    const int t = 2 * JP0 + j + d1 - T0;                                                                 \
                    if (t >= 0 && t < 8)                                                                                 \
                        mma_f16(acc[t], Fa[buf][d1][0], Fa[buf][d1][1], Fa[buf][d1][2], Fa[buf][d1][3],                  \
                                B[buf][j >> 1][2 * (j & 1)], B[buf][j >> 1][2 * (j & 1) + 1]);                           \
                }                                                                                                        \
            }                                                                                                            \
        } while (0)
        DENSE_LOAD(0, 0);
#pragma unroll 1
        for (int s = 0; s < 8; s += 2) {
            DENSE_LOAD(1, s + 1);
            DENSE_MMA(0);
            DENSE_LOAD(0, (s + 2) & 7);
            DENSE_MMA(1);
        }
#undef DENSE_LOAD
#undef DENSE_MMA
        const uint32_t kc = (uint32_t)__half_as_ushort(__float2half_rn(ldsf(tab + TO_MISC + 4)));
        const int r0 = g - 2 * c + 5, r1 = g - 2 * c - 11;
        const uint32_t c0 = (r0 == 0 ? kc : 0u) | (r0 == 1 ? kc << 16 : 0u);
        const uint32_t c2 = (r0 == 8 ? kc : 0u) | (r0 == 9 ? kc << 16 : 0u);
        const uint32_t e1 = (r1 == -8 ? kc : 0u) | (r1 == -7 ? kc << 16 : 0u);
        const uint32_t a = td + 16 * 64;
        const uint32_t f0 = lds32(a), f1 = lds32(a + 16), f2 = lds32(a - 16), f3 = lds32(a);
#pragma unroll
        for (int jp = 0; jp < (HALF ? 6 : 2); jp++) {
            uint32_t b[4];
            ldsm4(ub + (16 * jp) * 16, b[0], b[1], b[2], b[3]);
#pragma unroll
            for (int k = 0; k < 2; k++) {
                const int t4 = 2 * jp + k + 4 - T0, t8 = 2 * jp + k + 8 - T0;
                if (t4 >= 0 && t4 < 8) mma_f16(acc[t4], f0, f1, f2, f3, b[2 * k], b[2 * k + 1]);
                if (t8 >= 0 && t8 < 8) mma_f16(acc[t8], c0, 0u, c2, c0, b[2 * k], b[2 * k + 1]);
            }
        }
#pragma unroll
        for (int jp = 0; jp < (HALF ? 5 : 1); jp++) {
            uint32_t b[4];
            ldsm4(ub + (16 * jp - 7) * 16, b[0], b[1], b[2], b[3]);
#pragma unroll
            for (int k = 0; k < 2; k++) {
                const int t7 = 2 * jp + k + 7 - T0;
                if (t7 >= 0 && t7 < 8) mma_f16(acc[t7], 0u, e1, 0u, 0u, b[2 * k], b[2 * k + 1]);
            }
        }
    }
    if (threadIdx.x == 128) TMARK(27);
    mbar_wait(winbar, 0);
#pragma unroll 1
    for (int nu = 0; nu < 4; nu++) {
        const uint32_t tb = tab + TO_T2 + ((nu * 2 + par) * T2_P + gh - c - 8) * 4;
        uint32_t Ff[6][2];
#pragma unroll
        for (int i = 0; i < 6; i++) { Ff[i][0] = lds32(tb + 16 * (4 + i)); Ff[i][1] = lds32(tb + 16 * (3 + i)); }
        const int sg0 = 2 * (8 * (lm >> 1) + lr) + (lm & 1) - (nu >> 1);
        const uint32_t sb = (nu & 1) == 0 ? wb + WO_W5 + (sg0 & 1) * W5_PL + ((sg0 >> 1) + 17) * 16
                                          : wb + WO_W3 + (sg0 & 1) * W3_PL + ((sg0 >> 1) + 1) * 16;
#pragma unroll
        for (int kt = (HALF ? 0 : -1); kt < (HALF ? 6 : 2); kt++) {
            if (kt == -1 && nu != 0) continue;
            uint32_t a0, a1, a2, a3;
            ldsm4t(sb + kt * 256, a0, a1, a2, a3);
#pragma unroll
            for (int t = T0; t < T0 + 8; t++) {
                const int tau = t >> 1;
                if (kt >= tau - 4 && kt <= tau - 2 && !(kt == -1 && t < 3)) {
                    const int tp = t - 2 * kt;
                    mma_f16(acc[t - T0], a0, a1, a2, a3, Ff[tp - 4][0], Ff[tp - 4][1]);
                }
            }
        }
    }
#pragma unroll 1
    for (int nu = 0; nu < (HALF ? 2 : 1); nu++) {
        const uint32_t tb = tab + TO_T3 + ((nu * 2 + par) * T3_P + gh - c - 20) * 4;
        uint32_t Ff[10][2];
#pragma unroll
        for (int i = 0; i < 10; i++) {
            if (HALF || i == 1) { Ff[i][0] = lds32(tb + 16 * (8 + i)); Ff[i][1] = lds32(tb + 16 * (7 + i)); }
        }
        const int sg0 = 2 * (8 * (lm >> 1) + lr) + (lm & 1) - nu;
        const uint32_t sb = nu == 0 ? wb + WO_W9 + (sg0 & 1) * W9_PL + ((sg0 >> 1) + 16) * 16
                                    : wb + WO_W7 + (sg0 & 1) * W7_PL + ((sg0 >> 1) + 1) * 16;
#pragma unroll
        for (int kt = -1; kt < (HALF ? 4 : 0); kt++) {
            if (kt == -1 && nu != 0) continue;
            uint32_t a0, a1, a2, a3;
            ldsm4t(sb + kt * 256, a0, a1, a2, a3);
#pragma unroll
            for (int t = (HALF ? 8 : 7); t < T0 + 8; t++) {
                if (16 * kt <= 8 * t - 57) {
                    const int tp = t - 2 * kt;
                    mma_f16(acc[t - T0], a0, a1, a2, a3, Ff[tp - 8][0], Ff[tp - 8][1]);
                }
            }
        }
    }
    const float kinv = ldsf(tab + TO_MISC);
    if (threadIdx.x == 128) TMARK(19);
    if (HALF == 0) mbar_wait(os0bar, 0);
    __syncwarp();
    const uint32_t OS = HALF ? wb + WO_W7 : os0;
#pragma unroll
    for (int t = 0; t < 8; t += 2) {
        uint32_t uu[4], r[4];
        ldsm4t(ub + (8 * (T0 + t)) * 16, uu[0], uu[1], uu[2], uu[3]);
#pragma unroll
        for (int k = 0; k < 2; k++) {
            const uint32_t ya = pack_bf(acc[t + k][0] * kinv, acc[t + k][1] * kinv), yb = pack_bf(acc[t + k][2] * kinv, acc[t + k][3] * kinv);
            const uint32_t sa = pack_bf(h_lo(uu[2 * k]) * dsk, h_hi(uu[2 * k]) * dsk);
            const uint32_t sb2 = pack_bf(h_lo(uu[2 * k + 1]) * dsk, h_hi(uu[2 * k + 1]) * dsk);
            asm("add.rn.bf16x2 %0, %1, %2;" : "=r"(r[2 * k]) : "r"(ya), "r"(sa));
            asm("add.rn.bf16x2 %0, %1, %2;" : "=r"(r[2 * k + 1]) : "r"(yb), "r"(sb2));
        }
        stsm4t(OS + (8 * (t + (lm >> 1)) + lr) * 32 + (lm & 1) * 16, r[0], r[1], r[2], r[3]);
    }
    __syncwarp();
#pragma unroll
    for (int i = 0; i < 4; i++)
        reinterpret_cast<uint4*>(gout + HALF * 1024)[i * 32 + lane] = lds128(OS + (i * 32 + lane) * 16);
    mbar_arrive(donebar);
}

__global__ void __cluster_dims__(2, 1, 1) __launch_bounds__(NTHREADS, 1)
fused_kernel(const __grid_constant__ CUtensorMap tm_xn, const __grid_constant__ CUtensorMap tm_wg,
             const __grid_constant__ CUtensorMap tm_wu, const __grid_constant__ CUtensorMap tm_hst,
             const __grid_constant__ CUtensorMap tm_hld, const __grid_constant__ CUtensorMap tm_wd,
             const __grid_constant__ CUtensorMap tm_x2, const __grid_constant__ CUtensorMap tm_at,
             const __grid_constant__ CUtensorMap tm_out, const __grid_constant__ CUtensorMap tm_u,
             const __grid_constant__ CUtensorMap tm_xnst, const __grid_constant__ CUtensorMap tm_xtst, const Params P) {
    extern __shared__ __align__(1024) uint8_t smem[];
    const uint32_t sb = s2u(smem);
    const int tid = threadIdx.x, warp = tid >> 5, lane = tid & 31;
    const int cta = blockIdx.x, pair = cta >> 1, rank = cta & 1;
    const int fj = pair & 7, rb = 2 * (pair >> 3) + rank;
    const int rb2 = pair >> 2, nb2 = (pair & 3) * 128;
    const int nc2 = nb2 + rank * 64;
    const uint32_t bFull1 = sb + OFF_BAR, bEmpty1 = bFull1 + 64, bFull2 = bFull1 + 128, bEmpty2 = bFull1 + 160;
    const uint32_t bEpi = bFull1 + 192, bXT = bFull1 + 200, bR3 = bFull1 + 208, bPeer = bFull1 + 216, bXch = bFull1 + 224;
    const uint32_t bStg = bFull1 + 232, bTab = bFull1 + 248, bCin = bFull1 + 264, bCdone = bFull1 + 296, sEpoch = bFull1 + 256, bIn = bFull1 + 328, bLN = bFull1 + 336, bKp = bFull1 + 344, bWin = bFull1 + 352;

    uint4 xr[2][2];
    KgIn kin;
    uint16_t dsk_raw = 0;
    if (warp < 8) {
#pragma unroll
        for (int k = 0; k < 2; k++) {
            const uint4* src = reinterpret_cast<const uint4*>(P.x + (size_t)(16 * cta + 2 * warp + k) * D_);
            xr[k][0] = __ldg(src + lane);
            xr[k][1] = __ldg(src + 32 + lane);
        }
        kin = kgen_load(P, cta * 4 + (warp >> 1), warp & 1, lane);
        dsk_raw = __ldg(reinterpret_cast<const uint16_t*>(P.dsk + cta * 4 + (warp & 3)));
    }
    if (tid == 256) {
        TMARK(0);
        for (int i = 0; i < NST1; i++) { mbar_init(bFull1 + 8 * i, 1); mbar_init(bEmpty1 + 8 * i, 4); }
        for (int i = 0; i < 4; i++) {
            mbar_init(bFull2 + 8 * i, 1); mbar_init(bEmpty2 + 8 * i, 1);
            mbar_init(bCin + 8 * i, 1); mbar_init(bCdone + 8 * i, 64); mbar_init(bWin + 8 * i, 64);
        }
        mbar_init(bEpi, 1); mbar_init(bXT, 1); mbar_init(bLN, 256); mbar_init(bKp, 256); mbar_init(bR3, 1); mbar_init(bPeer, 1); mbar_init(bXch, 1);
        mbar_init(bStg, 128); mbar_init(bStg + 8, 128); mbar_init(bTab, 1); mbar_init(bIn, 2);
        asm volatile("fence.mbarrier_init.release.cluster;" ::: "memory");
    }
    __syncthreads();
    cluster_arrive();

    const int wgi = __shfl_sync(0xffffffffu, tid >> 7, 0);
    if (wgi == 2) {
        asm volatile("setmaxnreg.dec.sync.aligned.u32 40;");
        cluster_wait();
        if (warp == 8) {
            const CUtensorMap* tw = rank == 0 ? &tm_wg : &tm_wu;
            if (lane == 0) {
                for (int it = 0; it < 5; it++) {
                    if (it == 2) continue;
                    mbar_expect(bFull1 + 8 * it, ST_BYTES);
                    const uint32_t dst = sb + it * ST_BYTES + 8192 + rank * 12288;
#pragma unroll
                    for (int b = 0; b < 3; b++) tma2d_mc(dst + b * 4096, tw, fj * BF + 64 * b, it * 32, bFull1 + 8 * it, 3);
                }
            }
            __syncwarp();
            bar_sync(9, 64);
            if (lane == 0) {
                const unsigned epoch = lds32(sEpoch);
                mbar_wait(bXT, 0);
                wait_counter(&g_cnt[32 * (25 + rb)], (epoch + 1) * 8);
                TMARK(3);
                for (int it = 0; it < 2; it++) tma2d(sb + it * ST_BYTES, &tm_xn, it * 32, rb * 128, bFull1 + 8 * it);
                int st = 2, use = 0;
                for (int it = 2; it < G1_ITERS; it++) {
                    const bool init = st == 2 || st >= 5;
                    const bool pre = it == 3 || it == 4;
                    if (!pre) {
                        mbar_wait(bEmpty1 + 8 * st, init ? (use & 1) : ((use - 1) & 1));
                        mbar_expect(bFull1 + 8 * st, ST_BYTES);
                    }
                    tma2d(sb + st * ST_BYTES, &tm_xn, it * 32, rb * 128, bFull1 + 8 * st);
                    if (!pre) {
                        const uint32_t dst = sb + st * ST_BYTES + 8192 + rank * 12288;
#pragma unroll
                        for (int b = 0; b < 3; b++) tma2d_mc(dst + b * 4096, tw, fj * BF + 64 * b, it * 32, bFull1 + 8 * st, 3);
                    }
                    if (++st == NST1) { st = 0; use++; }
                }
                const int k0 = rank * 704;
                for (int kb = 0; kb < 3; kb++) {
                    mbar_wait(bEmpty1 + 8 * (4 + kb), kb == 0 ? 1 : 0);
                    mbar_expect(bFull2 + 8 * kb, ST_BYTES);
                    const uint32_t dst = sb + (4 + kb) * ST_BYTES + 16384;
                    tma2d(dst, &tm_wd, nb2, k0 + kb * 64, bFull2 + 8 * kb);
                    tma2d(dst + 8192, &tm_wd, nb2 + 64, k0 + kb * 64, bFull2 + 8 * kb);
                }
                wait_counter(&g_cnt[32 * (1 + rb2) + 16 * rank], (epoch + 1) * 4);
                TMARK(15);
                for (int kb = 0; kb < G2_ITERS; kb++) {
                    const int s2 = kb & 3;
                    const uint32_t dst = sb + (s2 < 3 ? (4 + s2) * ST_BYTES : 0);
                    if (kb >= 3) {
                        if (kb == 3) mbar_wait(bR3, 0);
                        else mbar_wait(bEmpty2 + 8 * s2, ((kb >> 2) - 1) & 1);
                        mbar_expect(bFull2 + 8 * s2, ST_BYTES);
                        tma2d(dst + 16384, &tm_wd, nb2, k0 + kb * 64, bFull2 + 8 * s2);
                        tma2d(dst + 24576, &tm_wd, nb2 + 64, k0 + kb * 64, bFull2 + 8 * s2);
                    }
                    tma2d(dst, &tm_hld, k0 + kb * 64, rb2 * 128, bFull2 + 8 * s2);
                }
            }
        } else if (warp == 9) {
            const unsigned epoch = (*(volatile unsigned*)&g_cnt[0]) >> 7;
            if (lane == 0) sts32(sEpoch, epoch);
            __syncwarp();
            bar_sync(9, 64);
            bar_sync(10, 64);
            if (lane == 0) {
                mbar_wait(bLN, 0);
                tma3d_store(&tm_xnst, 0, 16 * cta, 0, sb);
                tma3d_store(&tm_xnst, 0, 16 * cta, 4, sb + ST_BYTES);
                tma2d_store(&tm_xtst, 16 * cta, 0, sb + 2 * ST_BYTES);
                tma2d_store(&tm_xtst, 16 * cta, 256, sb + 2 * ST_BYTES + 8192);
                bulk_commit();
                bulk_wait_read0();
                mbar_arrive(bXT);
                mbar_arrive_cta_n(bEmpty1 + 8 * 2, 0, 2);
                mbar_arrive_cta_n(bEmpty1 + 8 * 2, 1, 2);
                bulk_wait0();
                red_release(&g_cnt[32 * (25 + (cta >> 3))], 1);
                red_relaxed(&g_cnt[0], 1);
                TMARK(16);
                wait_counter(&g_cnt[0], (epoch + 1) * 128);
                mbar_wait(bTab, 0);
                mbar_wait(bIn, 0);
                for (int i = 0; i < 4; i++) {
                    const uint32_t ib = sb + OFF_IN + i * IN_BYTES;
                    mbar_expect(bCin + 8 * i, IN_BYTES);
                    tma4d(ib, &tm_u, 0, -8, 0, cta * 4 + i, bCin + 8 * i);
                    bulk_load(ib + 2 * U_PL, g_tab + (size_t)(cta * 4 + i) * TAB_BYTES, TAB_BYTES, bCin + 8 * i);
                }
                for (int w = 0; w < 2; w++) {
                    mbar_wait(bStg + 8 * w, 0);
                    tma2d_store(&tm_hst, fj * BF, rb * 128 + w * 64, sb + w * STG_BYTES);
                    bulk_commit();
                }
                bulk_wait_read0();
                mbar_arrive(bR3);
                bulk_wait0();
                red_release(&g_cnt[32 * (1 + rb) + 16 * (fj >> 2)], 1);
                TMARK(11);
            }
        } else if (warp == 10) {
            bar_sync(10, 64);
            if (lane == 0) {
                mbar_wait(bKp, 0);
                for (int i = 0; i < 4; i++) bulk_store(g_tab + (size_t)(cta * 4 + i) * TAB_BYTES, sb + OFF_KG + 2 * i * 8192, TAB_BYTES);
                bulk_commit();
                bulk_wait_read0();
                for (int i = 0; i < 4; i++) mbar_arrive_cta_n(bEmpty1 + 8 * (5 + (i >> 1)), i & 1, 2);
                bulk_wait0();
                mbar_arrive(bTab);
                TMARK(12);
                const unsigned epoch = lds32(sEpoch);
                mbar_expect(bXch, 32768);
                for (int i = 0; i < 4; i++) mbar_wait(bCdone + 8 * i, 0);
                mbar_arrive_cta(bPeer, rank ^ 1);
                red_release(&g_cnt[32 * (17 + (cta >> 4))], 1);
                TMARK(13);
                mbar_expect(bEpi, 32768);
                tma2d(sb + OFF_EX, &tm_x2, nc2, rb2 * 128, bEpi);
                wait_counter(&g_cnt[32 * (17 + (nc2 >> 6))], (epoch + 1) * 16);
                TMARK(14);
                tma2d(sb + OFF_EA, &tm_at, rb2 * 128, nc2, bEpi);
                tma2d(sb + OFF_EA + 8192, &tm_at, rb2 * 128 + 64, nc2, bEpi);
            }
        }
        __syncwarp();
        cluster_sync();
    } else {
        asm volatile("setmaxnreg.inc.sync.aligned.u32 232;");
        const int wg = warp >> 2;
        const int g = lane >> 2, c = lane & 3, lm = lane >> 3, lr = lane & 7;
        if (tid == 0) TMARK(1);
        {
            float v[2][16], s[2], q[2];
#pragma unroll
            for (int k = 0; k < 2; k++) {
#pragma unroll
                for (int h = 0; h < 2; h++) {
                    v[k][8 * h + 0] = bf_lo(xr[k][h].x); v[k][8 * h + 1] = bf_hi(xr[k][h].x); v[k][8 * h + 2] = bf_lo(xr[k][h].y); v[k][8 * h + 3] = bf_hi(xr[k][h].y);
                    v[k][8 * h + 4] = bf_lo(xr[k][h].z); v[k][8 * h + 5] = bf_hi(xr[k][h].z); v[k][8 * h + 6] = bf_lo(xr[k][h].w); v[k][8 * h + 7] = bf_hi(xr[k][h].w);
                }
                float a = 0.f;
#pragma unroll
                for (int i = 0; i < 16; i++) a += v[k][i];
                s[k] = a;
            }
#pragma unroll
            for (int o = 16; o; o >>= 1) {
                s[0] += __shfl_xor_sync(0xffffffffu, s[0], o);
                s[1] += __shfl_xor_sync(0xffffffffu, s[1], o);
            }
#pragma unroll
            for (int k = 0; k < 2; k++) {
                s[k] *= (1.0f / 512.0f);
                float a = 0.f;
#pragma unroll
                for (int i = 0; i < 16; i++) { const float d = v[k][i] - s[k]; a = fmaf(d, d, a); }
                q[k] = a;
            }
#pragma unroll
            for (int o = 16; o; o >>= 1) {
                q[0] += __shfl_xor_sync(0xffffffffu, q[0], o);
                q[1] += __shfl_xor_sync(0xffffffffu, q[1], o);
            }
            if (tid == 0) { if (q[0] == 123.456f) TMARK(31); TMARK(28); }
#pragma unroll
            for (int k = 0; k < 2; k++) {
                const float m = bfr(s[k]);
                const float den = bfr(sqrt_ap(bfr(bfr(q[k] * (1.0f / 512.0f)) + 1e-5f)));
                const float rc = rcp_ap(den);
                uint32_t o[8];
#pragma unroll
                for (int i = 0; i < 8; i++) {
                    const uint32_t d = pack_bf(v[k][2 * i] - m, v[k][2 * i + 1] - m);
                    o[i] = pack_bf(bf_lo(d) * rc, bf_hi(d) * rc);
                }
                const int row = 2 * warp + k;
                const uint32_t xa = sb + (lane >> 3) * 2048 + row * 128 + (((lane & 7) ^ (row & 7)) * 16);
                sts128(xa, make_uint4(o[0], o[1], o[2], o[3]));
                sts128(xa + ST_BYTES, make_uint4(o[4], o[5], o[6], o[7]));
            }
            if (tid == 0) TMARK(29);
            bar_sync(1, 256);
            if (tid == 0) TMARK(30);
            const uint32_t base = sb + (warp >> 2) * ST_BYTES + (warp & 3) * 2048 + ((lm & 1) * 8 + lr) * 128;
            const uint32_t tdst = sb + 2 * ST_BYTES + (64 * warp + g) * 32 + c * 4;
#pragma unroll
            for (int i = 0; i < 4; i++) {
                uint32_t r0, r1, r2, r3;
                ldsm4t(base + (((2 * i + (lm >> 1)) ^ lr) * 16), r0, r1, r2, r3);
                sts32(tdst + i * 512, pack_h(bf_lo(r0), bf_hi(r0)));
                sts32(tdst + i * 512 + 16, pack_h(bf_lo(r1), bf_hi(r1)));
                sts32(tdst + i * 512 + 256, pack_h(bf_lo(r2), bf_hi(r2)));
                sts32(tdst + i * 512 + 272, pack_h(bf_lo(r3), bf_hi(r3)));
            }
            fence_async_smem();
            mbar_arrive(bLN);
        }
        if (tid == 0) TMARK(2);
        asm volatile("" : "+r"(kin.vl), "+r"(kin.vi), "+r"(kin.vr), "+r"(kin.vc), "+h"(kin.ldt), "+r"(kin.ca.x), "+r"(kin.cb.x));
        kgen(kin, sb + OFF_KG + warp * 8192, sb + OFF_KG + (warp ^ 1) * 8192, warp & 1, lane, 5 + (warp >> 1));
        mbar_arrive(bKp);
        cluster_wait();
        if (tid == 0) TMARK(4);
        {
            float ag[88], au[88];
            int st = 0, ph = 0, pst = 0;
#pragma unroll 1
            for (int it = 0; it < G1_ITERS; it++) {
                mbar_wait(bFull1 + 8 * st, ph);
                if (tid == 0) TMARK(44 + it);
                WG_FENCE;
                const uint32_t sa = sb + st * ST_BYTES;
#pragma unroll
                for (int kk = 0; kk < 2; kk++) {
                    const uint64_t da = mkdesc<2>(sa + wg * 4096 + kk * 32, 16, 512);
                    const uint32_t bs = sa + 8192 + kk * 2048;
                    wgmma_ss_bf16_n176<0, 1>(ag, da, mkdesc<1>(bs, 4096, 1024), (it | kk) > 0);
                    wgmma_ss_bf16_n176<0, 1>(au, da, mkdesc<1>(bs + 12288, 4096, 1024), (it | kk) > 0);
                }
                WG_COMMIT;
                if (it > 0) {
                    WG_WAIT(1);
                    if ((tid & 127) < 2) mbar_arrive_cta(bEmpty1 + 8 * pst, tid & 1);
                }
                if (it == 11 && (tid & 127) == 2) mbar_arrive(bIn);
                pst = st;
                if (++st == NST1) { st = 0; ph ^= 1; }
            }
            WG_WAIT(0);
            bar_sync(1, 256);
            if (tid == 0) TMARK(5);
            const uint32_t sa = sb + wg * STG_BYTES + ((warp & 3) * 16 + (lm & 1) * 8 + lr) * (BF * 2) + (lm >> 1) * 16;
#pragma unroll
            for (int i = 0; i < 22; i += 2) {
                uint32_t r[4];
#pragma unroll
                for (int j = 0; j < 4; j++) {
                    const int idx = 4 * (i + (j >> 1)) + 2 * (j & 1);
                    const uint32_t gp = pack_bf(ag[idx], ag[idx + 1]);
                    const uint32_t up = pack_bf(au[idx], au[idx + 1]);
                    float ge[2];
#pragma unroll
                    for (int e = 0; e < 2; e++) {
                        const float gg = e ? bf_hi(gp) : bf_lo(gp);
                        const float z = gg * fmaf(0.044715f * 0.7978845608028654f, gg * gg, 0.7978845608028654f);
                        const float hg = 0.5f * gg;
                        ge[e] = fmaf(hg, tanh_ap(z), hg);
                    }
                    const uint32_t gb = pack_bf(ge[0], ge[1]);
                    asm("mul.rn.bf16x2 %0, %1, %2;" : "=r"(r[j]) : "r"(gb), "r"(up));
                }
                stsm4(sa + i * 16, r[0], r[1], r[2], r[3]);
            }
            fence_async_smem();
            mbar_arrive(bStg + 8 * wg);
        }
        if (tid == 0) TMARK(6);
        {
            const int i = warp & 3;
            const float dsk = __uint_as_float((uint32_t)dsk_raw << 16);
            const uint32_t ib = sb + OFF_IN + i * IN_BYTES, wb = sb + OFF_WORK + i * WORK_BYTES;
            if (wg == 1) conv_channel<1>(dsk, ib, wb, 0, 0, lane, bWin + 8 * i, bCin + 8 * i, bCdone + 8 * i, g_AT + (size_t)(cta * 4 + i) * L_);
            else conv_channel<0>(dsk, ib, wb, sb + 32768 + i * 2048, bR3, lane, bWin + 8 * i, bCin + 8 * i, bCdone + 8 * i, g_AT + (size_t)(cta * 4 + i) * L_);
            if (tid == 128) TMARK(7);
            if (tid == 0) TMARK(24);
        }
        if (wg == 0) {
            float acc[2][64];
#pragma unroll 1
            for (int kb = 0; kb < G2_ITERS; kb++) {
                const int st = kb & 3;
                mbar_wait(bFull2 + 8 * st, (kb >> 2) & 1);
                if (tid == 0) TMARK(32 + kb);
                WG_FENCE;
                const uint32_t as = sb + (st < 3 ? (4 + st) * ST_BYTES : 0);
                const uint32_t bs = as + 16384;
#pragma unroll
                for (int kk = 0; kk < 4; kk++) {
                    const uint64_t db = mkdesc<1>(bs + kk * 2048, 8192, 1024);
                    wgmma_ss_bf16_n128<0, 1>(acc[0], mkdesc<1>(as + kk * 32, 16, 1024), db, (kb | kk) > 0);
                    wgmma_ss_bf16_n128<0, 1>(acc[1], mkdesc<1>(as + 8192 + kk * 32, 16, 1024), db, (kb | kk) > 0);
                }
                WG_COMMIT;
                if (kb > 0) {
                    WG_WAIT(1);
                    if (tid == 0) mbar_arrive(bEmpty2 + 8 * ((kb - 1) & 3));
                }
            }
            WG_WAIT(0);
            if (tid == 0) TMARK(8);
            mbar_wait(bPeer, 0);
            {
                const uint32_t rx = mapa(sb + OFF_XCH + tid * 16, rank ^ 1), rbar = mapa(bXch, rank ^ 1);
#pragma unroll
                for (int mb = 0; mb < 2; mb++)
#pragma unroll
                    for (int i = 0; i < 8; i++) {
                        const float v0 = rank ? acc[mb][4 * i] : acc[mb][32 + 4 * i], v1 = rank ? acc[mb][4 * i + 1] : acc[mb][33 + 4 * i];
                        const float v2 = rank ? acc[mb][4 * i + 2] : acc[mb][34 + 4 * i], v3 = rank ? acc[mb][4 * i + 3] : acc[mb][35 + 4 * i];
                        st_async4(rx + (mb * 8 + i) * 2048, v0, v1, v2, v3, rbar);
                    }
            }
            mbar_wait(bXch, 0);
            uint32_t ffn[2][16];
#pragma unroll
            for (int mb = 0; mb < 2; mb++)
#pragma unroll
                for (int i = 0; i < 8; i++) {
                    const uint4 o = lds128(sb + OFF_XCH + tid * 16 + (mb * 8 + i) * 2048);
                    const int b = 4 * i;
                    ffn[mb][2 * i] = pack_bf((rank ? acc[mb][32 + b] : acc[mb][b]) + __uint_as_float(o.x),
                                             (rank ? acc[mb][33 + b] : acc[mb][b + 1]) + __uint_as_float(o.y));
                    ffn[mb][2 * i + 1] = pack_bf((rank ? acc[mb][34 + b] : acc[mb][b + 2]) + __uint_as_float(o.z),
                                                 (rank ? acc[mb][35 + b] : acc[mb][b + 3]) + __uint_as_float(o.w));
                }
            mbar_wait(bEpi, 0);
            if (tid == 0) TMARK(9);
            const int lu = warp * 2 + (lm & 1);
#pragma unroll
            for (int mb = 0; mb < 2; mb++) {
                const uint32_t xa = sb + OFF_EX + (mb * 64 + warp * 16 + (lm & 1) * 8 + lr) * 128;
                const uint32_t at = sb + OFF_EA + mb * 8192;
#pragma unroll
                for (int i = 0; i < 8; i += 2) {
                    uint32_t xv[4], av[4], r[4];
                    const int iu = i + (lm >> 1);
                    ldsm4(xa + ((iu ^ lr) * 16), xv[0], xv[1], xv[2], xv[3]);
                    ldsm4t(at + (8 * iu + lr) * 128 + ((lu ^ lr) * 16), av[0], av[1], av[2], av[3]);
#pragma unroll
                    for (int j = 0; j < 4; j++) {
                        uint32_t t1;
                        asm("add.rn.bf16x2 %0, %1, %2;" : "=r"(t1) : "r"(xv[j]), "r"(av[j]));
                        asm("add.rn.bf16x2 %0, %1, %2;" : "=r"(r[j]) : "r"(t1), "r"(ffn[mb][2 * i + j]));
                    }
                    stsm4(xa + ((iu ^ lr) * 16), r[0], r[1], r[2], r[3]);
                }
            }
            fence_async_smem();
            bar_sync(3, 128);
            if (tid == 0) {
                tma2d_store(&tm_out, nc2, rb2 * 128, sb + OFF_EX);
                bulk_commit();
                bulk_wait_read0();
                TMARK(10);
            }
        }
        __syncwarp();
        cluster_sync();
    }
}

typedef CUresult (*EncodeFn)(CUtensorMap*, CUtensorMapDataType, cuuint32_t, void*, const cuuint64_t*, const cuuint64_t*,
                             const cuuint32_t*, const cuuint32_t*, CUtensorMapInterleave, CUtensorMapSwizzle,
                             CUtensorMapL2promotion, CUtensorMapFloatOOBfill);

static void make_map(EncodeFn fn, CUtensorMap* m, void* ptr, int rank, const cuuint64_t* dims, const cuuint64_t* strides,
                     const cuuint32_t* box, CUtensorMapSwizzle sw) {
    cuuint32_t es[5] = {1, 1, 1, 1, 1};
    fn(m, CU_TENSOR_MAP_DATA_TYPE_BFLOAT16, rank, ptr, dims, strides, box, es, CU_TENSOR_MAP_INTERLEAVE_NONE, sw,
       CU_TENSOR_MAP_L2_PROMOTION_L2_256B, CU_TENSOR_MAP_FLOAT_OOB_FILL_NONE);
}

}

extern "C" void kernel_launch(void* const* d_in, const int* in_sizes, int n_in, void* d_out, int out_size) {
    using namespace fk;
    static EncodeFn fn = nullptr;
    static void *p_h = nullptr, *p_at = nullptr, *p_xn = nullptr, *p_xnT = nullptr;
    if (!fn) {
        void* f = nullptr;
        cudaDriverEntryPointQueryResult qr;
        cudaGetDriverEntryPoint("cuTensorMapEncodeTiled", &f, cudaEnableDefault, &qr);
        fn = (EncodeFn)f;
        cudaGetSymbolAddress(&p_h, g_h);
        cudaGetSymbolAddress(&p_at, g_AT);
        cudaGetSymbolAddress(&p_xn, g_xn);
        cudaGetSymbolAddress(&p_xnT, g_xnT);
        cudaFuncSetAttribute(fused_kernel, cudaFuncAttributeMaxDynamicSharedMemorySize, SMEM_BYTES);
    }
    void* x = d_in[0];
    CUtensorMap tm_xn, tm_wg, tm_wu, tm_hst, tm_hld, tm_wd, tm_x2, tm_at, tm_out, tm_u, tm_xnst, tm_xtst;
    {
        cuuint64_t d[2] = {(cuuint64_t)D_, (cuuint64_t)L_}, s[1] = {(cuuint64_t)D_ * 2};
        cuuint32_t b[2] = {32, 128};
        make_map(fn, &tm_xn, p_xn, 2, d, s, b, CU_TENSOR_MAP_SWIZZLE_64B);
        cuuint32_t b2[2] = {64, 128};
        make_map(fn, &tm_x2, x, 2, d, s, b2, CU_TENSOR_MAP_SWIZZLE_128B);
        make_map(fn, &tm_out, d_out, 2, d, s, b2, CU_TENSOR_MAP_SWIZZLE_128B);
    }
    {
        cuuint64_t d[2] = {(cuuint64_t)F_, (cuuint64_t)D_}, s[1] = {(cuuint64_t)F_ * 2};
        cuuint32_t b[2] = {64, 32};
        make_map(fn, &tm_wg, d_in[8], 2, d, s, b, CU_TENSOR_MAP_SWIZZLE_128B);
        make_map(fn, &tm_wu, d_in[9], 2, d, s, b, CU_TENSOR_MAP_SWIZZLE_128B);
    }
    {
        cuuint64_t d[2] = {(cuuint64_t)F_, (cuuint64_t)L_}, s[1] = {(cuuint64_t)F_ * 2};
        cuuint32_t b[2] = {(cuuint32_t)BF, 64};
        make_map(fn, &tm_hst, p_h, 2, d, s, b, CU_TENSOR_MAP_SWIZZLE_NONE);
        cuuint32_t b2[2] = {64, 128};
        make_map(fn, &tm_hld, p_h, 2, d, s, b2, CU_TENSOR_MAP_SWIZZLE_128B);
    }
    {
        cuuint64_t d[2] = {(cuuint64_t)D_, (cuuint64_t)F_}, s[1] = {(cuuint64_t)D_ * 2};
        cuuint32_t b[2] = {64, 64};
        make_map(fn, &tm_wd, d_in[10], 2, d, s, b, CU_TENSOR_MAP_SWIZZLE_128B);
    }
    {
        cuuint64_t d[2] = {(cuuint64_t)L_, (cuuint64_t)D_}, s[1] = {(cuuint64_t)L_ * 2};
        cuuint32_t b[2] = {64, 64};
        make_map(fn, &tm_at, p_at, 2, d, s, b, CU_TENSOR_MAP_SWIZZLE_128B);
    }
    {
        cuuint64_t d[4] = {8, 128, 2, (cuuint64_t)D_}, s[3] = {32, 16, (cuuint64_t)L_ * 2};
        cuuint32_t b[4] = {8, 136, 2, 1};
        make_map(fn, &tm_u, p_xnT, 4, d, s, b, CU_TENSOR_MAP_SWIZZLE_NONE);
    }
    {
        cuuint64_t d[3] = {64, (cuuint64_t)L_, 8}, s[2] = {1024, 128};
        cuuint32_t b[3] = {64, 16, 4};
        make_map(fn, &tm_xnst, p_xn, 3, d, s, b, CU_TENSOR_MAP_SWIZZLE_128B);
    }
    {
        cuuint64_t d[2] = {(cuuint64_t)L_, (cuuint64_t)D_}, s[1] = {(cuuint64_t)L_ * 2};
        cuuint32_t b[2] = {16, 256};
        make_map(fn, &tm_xtst, p_xnT, 2, d, s, b, CU_TENSOR_MAP_SWIZZLE_NONE);
    }
    Params P;
    P.x = (const __nv_bfloat16*)d_in[0];
    P.lar = (const __nv_bfloat16*)d_in[1];
    P.aim = (const __nv_bfloat16*)d_in[2];
    P.cre = (const __nv_bfloat16*)d_in[3];
    P.cim = (const __nv_bfloat16*)d_in[4];
    P.ldt = (const __nv_bfloat16*)d_in[5];
    P.dsk = (const __nv_bfloat16*)d_in[6];
    fused_kernel<<<128, NTHREADS, SMEM_BYTES>>>(tm_xn, tm_wg, tm_wu, tm_hst, tm_hld, tm_wd, tm_x2, tm_at, tm_out, tm_u, tm_xnst, tm_xtst, P);
}
```
